```python
import torch

def _softmax(x, axis=-1):
    return torch.softmax(x, dim=axis)
def _gelu(x):
    return torch.nn.functional.gelu(x, approximate="tanh")
def _silu(x):
    return torch.nn.functional.silu(x)
def _sigmoid(x):
    return torch.sigmoid(x)
def _layernorm(x, axis=-1, eps=1e-5):
    m = x.mean(dim=axis, keepdim=True)
    v = x.var(dim=axis, keepdim=True, unbiased=False)
    return (x - m) / torch.sqrt(v + eps)
def _scatter_add(tgt, idx, src, axis=0):
    return tgt.clone().index_add_(axis, idx, src)
def _segment_sum(src, seg, n):
    out = torch.zeros((n,) + src.shape[1:], dtype=src.dtype)
    return out.index_add_(0, seg, src)
def _pad(x, pw):
    flat = tuple(v for pair in reversed(pw) for v in pair)
    return torch.nn.functional.pad(x, flat)

kernel_name = 'standalone__attention_interact_autoint__recsys'

def setup_inputs():

    _w = (lambda a: (lambda t: t.to(torch.bfloat16) if t.is_floating_point() else t)(torch.as_tensor(a)))
    B, F = 4096, 100
    D = max(2, (16 // 2) * 2)
    H = 2
    Dh = D // H
    return {
        "e": _w((lambda *s: torch.randn(*s, dtype=torch.bfloat16) * 0.05)(B, F, D).to(float)),
        "wq": _w((lambda *s: torch.randn(*s, dtype=torch.bfloat16) * 6.4)(H, D, Dh).to(float)),
        "wk": _w((lambda *s: torch.randn(*s, dtype=torch.bfloat16) * 6.4)(H, D, Dh).to(float)),
        "wv": _w((lambda *s: torch.randn(*s, dtype=torch.bfloat16) * 0.05)(H, D, Dh).to(float)),
        "wres": _w((lambda *s: torch.randn(*s, dtype=torch.bfloat16) * 0.05)(D, D).to(float)),
    }

def reference(e, wq, wk, wv, wres):
    H, D, Dh = wq.shape[0], wq.shape[1], wq.shape[2]
    B, F = e.shape[0], e.shape[1]
    q = torch.einsum('bfd,hdk->bhfk', e, wq)
    k = torch.einsum('bfd,hdk->bhfk', e, wk)
    v = torch.einsum('bfd,hdk->bhfk', e, wv)
    scale = float(Dh) ** -0.5
    scores = torch.einsum('bhfk,bhgk->bhfg', q, k) * scale
    attn = _softmax(scores, axis=-1)
    attn = (lambda x, dt: x.to(dt))(attn, v.dtype)
    ctx = torch.einsum('bhfg,bhgk->bhfk', attn, v)
    ctx = (lambda x, *d: x.permute(*d))(ctx, 0, 2, 1, 3).reshape(B, F, H * Dh)
    res = torch.einsum('bfd,de->bfe', e, wres)
    out = ctx + res
    mask = (lambda x, dt: x.to(dt))(out > 0, out.dtype)
    return out * mask
```

```cpp
#include <cuda_runtime.h>
#include <cuda_bf16.h>
#include <stdint.h>

#define NWG 3
#define TAIL 1
#define ZPERS 1
#define MUMASK 0x1111111u
#define PROF_MARK(i)
#define PROF_GT(i)

namespace {

constexpr int F = 100;
constexpr int EB = 3200;
constexpr int MAXB = 32;
constexpr int COL = 1792;
constexpr int OFF_K = 0;
constexpr int OFF_V = 4 * COL;
constexpr int OFF_O = 7 * COL;
constexpr int BUF = OFF_O + 3072;
constexpr int SM_BUF = 0;
constexpr int SM_W = SM_BUF + NWG * 2 * BUF;
constexpr int SM_E = SM_W + 2048;
constexpr int SM_BAR = SM_E + MAXB * EB;
constexpr int SM_RED = SM_BAR + 64;
constexpr int SM_C = SM_RED + 64;
constexpr int SM_TOTAL = SM_C + 512;

constexpr float QSCALE = 0.35355339059327373f * 1.4426950408889634f;
constexpr float SLIMIT = 90.0f;

__device__ __forceinline__ uint64_t mkdesc(uint32_t addr, uint32_t lbo, uint32_t sbo) {
    return (uint64_t)((addr & 0x3FFFF) >> 4) | ((uint64_t)(lbo >> 4) << 16) | ((uint64_t)(sbo >> 4) << 32);
}
#define WG_ARRIVE() asm volatile("wgmma.fence.sync.aligned;" ::: "memory")
#define WG_COMMIT() asm volatile("wgmma.commit_group.sync.aligned;" ::: "memory")
#define WG_WAIT(n) asm volatile("wgmma.wait_group.sync.aligned " #n ";" ::: "memory")
template <int N> __device__ __forceinline__ void pin(float* d) {
#pragma unroll
    for (int i = 0; i < N; i++) asm volatile("" : "+f"(d[i])::"memory");
}
template <int N> __device__ __forceinline__ void pin(uint32_t* d) {
#pragma unroll
    for (int i = 0; i < N; i++) asm volatile("" : "+r"(d[i])::"memory");
}
#define O4(c, d, i) c(d[i]), c(d[i + 1]), c(d[i + 2]), c(d[i + 3])
#define O8(c, d, i) O4(c, d, i), O4(c, d, i + 4)

template <int SEL>
__device__ __forceinline__ void qk48(float* d, uint32_t a0, uint32_t a1, uint32_t a2, uint32_t a3, uint64_t b, uint32_t meta) {
    asm volatile("wgmma.mma_async.sp.sync.aligned.m64n48k32.f32.bf16.bf16 "
                 "{%0,%1,%2,%3,%4,%5,%6,%7,%8,%9,%10,%11,%12,%13,%14,%15,%16,%17,%18,%19,%20,%21,%22,%23},"
                 "{%24,%25,%26,%27}, %28, %29, %30, 0, 1, 1, 0;"
                 : O8("=f", d, 0), O8("=f", d, 8), O8("=f", d, 16)
                 : "r"(a0), "r"(a1), "r"(a2), "r"(a3), "l"(b), "r"(meta), "n"(SEL));
}
template <int SEL>
__device__ __forceinline__ void qk56(float* d, uint32_t a0, uint32_t a1, uint32_t a2, uint32_t a3, uint64_t b, uint32_t meta) {
    asm volatile("wgmma.mma_async.sp.sync.aligned.m64n56k32.f32.bf16.bf16 "
                 "{%0,%1,%2,%3,%4,%5,%6,%7,%8,%9,%10,%11,%12,%13,%14,%15,%16,%17,%18,%19,%20,%21,%22,%23,%24,%25,%26,%27},"
                 "{%28,%29,%30,%31}, %32, %33, %34, 0, 1, 1, 0;"
                 : O8("=f", d, 0), O8("=f", d, 8), O8("=f", d, 16), O4("=f", d, 24)
                 : "r"(a0), "r"(a1), "r"(a2), "r"(a3), "l"(b), "r"(meta), "n"(SEL));
}
__device__ __forceinline__ void proj64(float* d, const uint32_t* a, uint64_t b) {
    asm volatile("wgmma.mma_async.sync.aligned.m64n64k16.f32.bf16.bf16 "
                 "{%0,%1,%2,%3,%4,%5,%6,%7,%8,%9,%10,%11,%12,%13,%14,%15,%16,%17,%18,%19,%20,%21,%22,%23,%24,%25,%26,%27,%28,%29,%30,%31},"
                 "{%32,%33,%34,%35}, %36, 0, 1, 1, 0;"
                 : O8("=f", d, 0), O8("=f", d, 8), O8("=f", d, 16), O8("=f", d, 24)
                 : "r"(a[0]), "r"(a[1]), "r"(a[2]), "r"(a[3]), "l"(b));
}
__device__ __forceinline__ void proj32(float* d, const uint32_t* a, uint64_t b) {
    asm volatile("wgmma.mma_async.sync.aligned.m64n32k16.f32.bf16.bf16 "
                 "{%0,%1,%2,%3,%4,%5,%6,%7,%8,%9,%10,%11,%12,%13,%14,%15},"
                 "{%16,%17,%18,%19}, %20, 0, 1, 1, 0;"
                 : O8("=f", d, 0), O8("=f", d, 8)
                 : "r"(a[0]), "r"(a[1]), "r"(a[2]), "r"(a[3]), "l"(b));
}
template <int N, bool FIRST> __device__ __forceinline__ void pv(float* d, const uint32_t* a, uint64_t b) {
    if (N == 16 && FIRST)
        asm volatile("wgmma.mma_async.sync.aligned.m64n16k16.f32.bf16.bf16 {%0,%1,%2,%3,%4,%5,%6,%7},{%8,%9,%10,%11}, %12, 0, 1, 1, 1;"
                     : O8("=f", d, 0) : "r"(a[0]), "r"(a[1]), "r"(a[2]), "r"(a[3]), "l"(b));
    if (N == 16 && !FIRST)
        asm volatile("wgmma.mma_async.sync.aligned.m64n16k16.f32.bf16.bf16 {%0,%1,%2,%3,%4,%5,%6,%7},{%8,%9,%10,%11}, %12, 1, 1, 1, 1;"
                     : O8("+f", d, 0) : "r"(a[0]), "r"(a[1]), "r"(a[2]), "r"(a[3]), "l"(b));
    if (N == 24 && FIRST)
        asm volatile("wgmma.mma_async.sync.aligned.m64n24k16.f32.bf16.bf16 {%0,%1,%2,%3,%4,%5,%6,%7,%8,%9,%10,%11},{%12,%13,%14,%15}, %16, 0, 1, 1, 1;"
                     : O8("=f", d, 0), O4("=f", d, 8) : "r"(a[0]), "r"(a[1]), "r"(a[2]), "r"(a[3]), "l"(b));
    if (N == 24 && !FIRST)
        asm volatile("wgmma.mma_async.sync.aligned.m64n24k16.f32.bf16.bf16 {%0,%1,%2,%3,%4,%5,%6,%7,%8,%9,%10,%11},{%12,%13,%14,%15}, %16, 1, 1, 1, 1;"
                     : O8("+f", d, 0), O4("+f", d, 8) : "r"(a[0]), "r"(a[1]), "r"(a[2]), "r"(a[3]), "l"(b));
}
__device__ __forceinline__ void mma16(float* d, uint32_t a0, uint32_t a1, uint32_t a2, uint32_t a3, uint32_t b0, uint32_t b1) {
    asm("mma.sync.aligned.m16n8k16.row.col.f32.bf16.bf16.f32 {%0,%1,%2,%3},{%4,%5,%6,%7},{%8,%9},{%0,%1,%2,%3};"
        : O4("+f", d, 0) : "r"(a0), "r"(a1), "r"(a2), "r"(a3), "r"(b0), "r"(b1));
}
__device__ __forceinline__ uint32_t pack(float lo, float hi) {
    uint32_t p; asm("cvt.rn.bf16x2.f32 %0, %1, %2;" : "=r"(p) : "f"(hi), "f"(lo)); return p;
}
__device__ __forceinline__ uint32_t pack_relu(float lo, float hi) {
    uint32_t p; asm("cvt.rn.relu.bf16x2.f32 %0, %1, %2;" : "=r"(p) : "f"(hi), "f"(lo)); return p;
}
__device__ __forceinline__ float ex2(float x) { float y; asm("ex2.approx.ftz.f32 %0, %1;" : "=f"(y) : "f"(x)); return y; }
__device__ __forceinline__ float rcp(float x) { float y; asm("rcp.approx.ftz.f32 %0, %1;" : "=f"(y) : "f"(x)); return y; }
__device__ __forceinline__ uint32_t amax2(uint32_t a, uint32_t b) {
    uint32_t d; asm("max.NaN.xorsign.abs.bf16x2 %0, %1, %2;" : "=r"(d) : "r"(a), "r"(b)); return d;
}
__device__ __forceinline__ uint32_t exp2_pair(float x0, float x1, uint32_t one2, uint32_t sh16) {
    uint32_t z, g, p;
    asm("mad.lo.u32 %0, %1, %2, %3;" : "=r"(z) : "r"(__float_as_uint(x1)), "r"(sh16), "r"(__float_as_uint(x0)));
    asm("lop3.b32 %0, %1, 0x007F007F, %2, 0xEA;" : "=r"(g) : "r"(z), "r"(one2));
    asm("fma.rn.bf16x2 %0, %1, %1, %2;" : "=r"(p) : "r"(g), "r"(0x40014001u));
    return p + z - g;
}
template <int T0, int NP> __device__ __forceinline__ void exp_block(const float* s, uint32_t* p, uint32_t one2, uint32_t sh16) {
#pragma unroll
    for (int i = 0; i < NP; i++) {
        if ((MUMASK >> (T0 + i)) & 1) p[i] = pack(ex2(s[2 * i]), ex2(s[2 * i + 1]));
        else p[i] = exp2_pair(s[2 * i], s[2 * i + 1], one2, sh16);
    }
}
__device__ __forceinline__ void ldsm4(uint32_t* r, uint32_t addr) {
    asm volatile("ldmatrix.sync.aligned.m8n8.x4.shared.b16 {%0,%1,%2,%3}, [%4];"
                 : "=r"(r[0]), "=r"(r[1]), "=r"(r[2]), "=r"(r[3]) : "r"(addr) : "memory");
}
__device__ __forceinline__ void ldsm4t(uint32_t* r, uint32_t addr) {
    asm volatile("ldmatrix.sync.aligned.m8n8.x4.trans.shared.b16 {%0,%1,%2,%3}, [%4];"
                 : "=r"(r[0]), "=r"(r[1]), "=r"(r[2]), "=r"(r[3]) : "r"(addr) : "memory");
}
__device__ __forceinline__ void stsm4(uint32_t addr, uint32_t a, uint32_t b, uint32_t c, uint32_t d) {
    asm volatile("stmatrix.sync.aligned.m8n8.x4.shared.b16 [%0], {%1,%2,%3,%4};" ::"r"(addr), "r"(a), "r"(b), "r"(c), "r"(d) : "memory");
}
__device__ __forceinline__ void stsm2(uint32_t addr, uint32_t a, uint32_t b) {
    asm volatile("stmatrix.sync.aligned.m8n8.x2.shared.b16 [%0], {%1,%2};" ::"r"(addr), "r"(a), "r"(b) : "memory");
}
__device__ __forceinline__ uint32_t movm(uint32_t a) {
    uint32_t d; asm volatile("movmatrix.sync.aligned.m8n8.trans.b16 %0, %1;" : "=r"(d) : "r"(a)); return d;
}
__device__ __forceinline__ void mbar_wait(uint32_t bar, uint32_t phase) {
    asm volatile("{.reg .pred p; .reg .b32 c;\n"
                 "mbarrier.try_wait.parity.shared::cta.b64 p, [%0], %1;\n"
                 "@p bra.uni DONE;\n"
                 "mov.b32 c, 0;\n"
                 "LOOP:\n"
                 "mbarrier.try_wait.parity.shared::cta.b64 p, [%0], %1;\n"
                 "@p bra.uni DONE;\n"
                 "add.u32 c, c, 1;\n"
                 "setp.lt.u32 p, c, 1000000;\n"
                 "@p bra.uni LOOP;\n"
                 "DONE:}" ::"r"(bar), "r"(phase) : "memory");
}
__device__ __forceinline__ void load_item(uint32_t dst, const void* src, uint32_t bar) {
    asm volatile("mbarrier.arrive.expect_tx.shared::cta.b64 _, [%0], %1;" ::"r"(bar), "n"(EB) : "memory");
    asm volatile("cp.async.bulk.shared::cluster.global.mbarrier::complete_tx::bytes [%0], [%1], %2, [%3];"
                 ::"r"(dst), "l"(src), "n"(EB), "r"(bar) : "memory");
}
__device__ __forceinline__ void store_item(void* dst, uint32_t src) {
    asm volatile("cp.async.bulk.global.shared::cta.bulk_group [%0], [%1], 3072;" ::"l"(dst), "r"(src) : "memory");
    asm volatile("cp.async.bulk.commit_group;" ::: "memory");
}
__device__ __forceinline__ bool elect() {
    uint32_t p;
    asm volatile("{.reg .pred p; elect.sync _|p, 0xffffffff; selp.u32 %0, 1, 0, p;}" : "=r"(p));
    return p;
}
__device__ __forceinline__ uint32_t ldc(uint32_t addr) {
    uint32_t r;
    asm volatile("ld.volatile.shared.b32 %0, [%1];" : "=r"(r) : "r"(addr) : "memory");
    return r;
}
__device__ __forceinline__ uint32_t keep(uint32_t v, uint32_t scratch) {
    asm volatile("st.volatile.shared.b32 [%0], %1;" ::"r"(scratch), "r"(v) : "memory");
    return ldc(scratch);
}
__device__ __forceinline__ uint64_t desc64(uint32_t lo, uint32_t hi) {
    uint64_t d; asm("mov.b64 %0, {%1, %2};" : "=l"(d) : "r"(lo), "r"(hi)); return d;
}
__device__ __forceinline__ uint32_t add_relu(uint32_t a, uint32_t b) {
    uint32_t d; asm("fma.rn.relu.bf16x2 %0, %1, %2, %3;" : "=r"(d) : "r"(a), "r"(0x3F803F80u), "r"(b)); return d;
}
__device__ __forceinline__ uint32_t fin(float o0, float o1, float l, uint32_t r) {
    const float i = rcp(l);
    return add_relu(pack(o0 * i, o1 * i), r);
}
__device__ __forceinline__ float bfr(float x) { return __bfloat162float(__float2bfloat16(x)); }

__device__ __noinline__ void slow_path(const __nv_bfloat16* e, const __nv_bfloat16* wq, const __nv_bfloat16* wk,
                                       const __nv_bfloat16* wv, const __nv_bfloat16* wr, __nv_bfloat16* out,
                                       float* kv, int t, int barid) {
    float x[16];
    if (t < F) {
        for (int d = 0; d < 16; d++) x[d] = __bfloat162float(e[t * 16 + d]);
        for (int c = 0; c < 16; c++) {
            float k = 0.f, v = 0.f;
            for (int d = 0; d < 16; d++) {
                k = fmaf(x[d], __bfloat162float(wk[(c >> 3) * 128 + d * 8 + (c & 7)]), k);
                v = fmaf(x[d], __bfloat162float(wv[(c >> 3) * 128 + d * 8 + (c & 7)]), v);
            }
            kv[t * 32 + c] = bfr(k);
            kv[t * 32 + 16 + c] = bfr(v);
        }
    }
    asm volatile("bar.sync %0, 128;" ::"r"(barid) : "memory");
    if (t < F) {
        for (int h = 0; h < 2; h++) {
            float q[8], acc[8];
            for (int c = 0; c < 8; c++) {
                float s = 0.f;
                for (int d = 0; d < 16; d++) s = fmaf(x[d], __bfloat162float(wq[h * 128 + d * 8 + c]), s);
                q[c] = bfr(s);
                acc[c] = 0.f;
            }
            float m = -INFINITY, l = 0.f;
            for (int pass = 0; pass < 3; pass++) {
                for (int j = 0; j < F; j++) {
                    float s = 0.f;
                    for (int c = 0; c < 8; c++) s = fmaf(q[c], kv[j * 32 + h * 8 + c], s);
                    s = bfr(bfr(s) * 0.35355339059327373f);
                    if (pass == 0) m = fmaxf(m, s);
                    else if (pass == 1) l += expf(s - m);
                    else {
                        float p = bfr(expf(s - m) / l);
                        for (int c = 0; c < 8; c++) acc[c] = fmaf(p, kv[j * 32 + 16 + h * 8 + c], acc[c]);
                    }
                }
            }
            for (int c = 0; c < 8; c++) {
                float r = 0.f;
                for (int d = 0; d < 16; d++) r = fmaf(x[d], __bfloat162float(wr[d * 16 + h * 8 + c]), r);
                float o = bfr(bfr(acc[c]) + bfr(r));
                out[t * 16 + h * 8 + c] = __float2bfloat16(o > 0.f ? o : o * 0.f);
            }
        }
    }
    asm volatile("bar.sync %0, 128;" ::"r"(barid) : "memory");
}

struct State {
    uint32_t qA[2], qB[2], qC[2];
    uint32_t r[6];
    uint32_t mq, mkA, mkB;
};
__device__ __forceinline__ void cvt_kv(State& st, const float* x, uint32_t aK) {
    uint32_t k[4];
#pragma unroll
    for (int i = 0; i < 4; i++) k[i] = pack(x[2 * i], x[2 * i + 1]);
    stsm4(aK, k[0], k[1], k[2], k[3]);
    stsm4(aK + OFF_V, pack(x[8], x[9]), pack(x[10], x[11]), pack(x[12], x[13]), pack(x[14], x[15]));
    st.mkA = amax2(amax2(st.mkA, k[0]), k[1]);
    st.mkB = amax2(amax2(st.mkB, k[2]), k[3]);
}
__device__ __forceinline__ void cvt_qr0(State& st, const float* x) {
    st.qA[0] = pack(x[0], x[1]);   st.qA[1] = pack(x[2], x[3]);
    st.qB[0] = pack(x[4], x[5]);   st.qB[1] = pack(x[6], x[7]);
#pragma unroll
    for (int i = 0; i < 4; i++) st.r[i] = pack(x[8 + 2 * i], x[9 + 2 * i]);
    st.mq = amax2(amax2(amax2(amax2(st.mq, st.qA[0]), st.qA[1]), st.qB[0]), st.qB[1]);
}
__device__ __forceinline__ void cvt_qr1(State& st, const float* x) {
    st.qC[0] = pack(x[0], x[1]);   st.qC[1] = pack(x[4], x[5]);
    st.r[4] = pack(x[8], x[9]);    st.r[5] = pack(x[12], x[13]);
    st.mq = amax2(amax2(st.mq, st.qC[0]), st.qC[1]);
}

__global__ void __launch_bounds__(NWG * 128, 1)
autoint_kernel(const __nv_bfloat16* __restrict__ e, const __nv_bfloat16* __restrict__ wq, const __nv_bfloat16* __restrict__ wk,
               const __nv_bfloat16* __restrict__ wv, const __nv_bfloat16* __restrict__ wr, __nv_bfloat16* __restrict__ out,
               int base, int rem, uint32_t sh16) {
    extern __shared__ __align__(1024) uint8_t smem[];
    PROF_MARK(0); PROF_GT(0);
    const uint32_t sb = (uint32_t)__cvta_generic_to_shared(smem);
    const int tid = threadIdx.x, lane = tid & 31;
    const int wg = __shfl_sync(0xffffffffu, tid >> 7, 0);
    const int w = __shfl_sync(0xffffffffu, (tid >> 5) & 3, 0);
    const int nb = base + ((int)blockIdx.x < rem);
    const int b0 = base * blockIdx.x + min((int)blockIdx.x, rem);
    const uint8_t* eg = (const uint8_t*)e + (size_t)b0 * EB;
    uint8_t* og = (uint8_t*)out + (size_t)b0 * EB;
    const uint32_t bar = sb + SM_BAR + wg * 16;
    const bool io_warp = w == (wg & 3);

    if (io_warp && elect()) {
        asm volatile("mbarrier.init.shared::cta.b64 [%0], 1;" ::"r"(bar) : "memory");
        asm volatile("mbarrier.init.shared::cta.b64 [%0], 1;" ::"r"(bar + 8) : "memory");
        asm volatile("fence.mbarrier_init.release.cluster;" ::: "memory");
        if (wg < nb) load_item(sb + SM_E + wg * EB, eg + wg * EB, bar);
    }
    uint2 wreg = make_uint2(0, 0);
    if (tid < 256) {
        const int a = tid >> 6;
        const __nv_bfloat16* src = a == 0 ? wk : a == 1 ? wv : a == 2 ? wq : wr;
        wreg = __ldg((const uint2*)src + (tid & 63));
    }
    if (tid < 32) {
        const int q = lane & 3;
        uint32_t* c = (uint32_t*)(smem + SM_C) + lane;
        c[0] = q < 3 ? 0x3FE03FE0u : 0x3F803F80u;
        c[32] = (q & 1) ? 0xEEEE4444u : (q ? 0xEEEEEEEEu : 0x44444444u);
        c[64] = 0xEEEE4444u;
        c[96] = 0x3F803F80u;
        if (lane < 4) ((uint32_t*)(smem + SM_RED))[lane] = 0;
    }
    {
        const int t = tid & 127;
        const uint32_t one = t < F ? 0x3F803F80u : 0u;
        const bool mlo = (MUMASK >> (2 * (t >> 3))) & 1, mhi = (MUMASK >> (2 * (t >> 3) + 1)) & 1;
        const uint32_t big = 0x45C045C0u;
        const uint32_t fn = (t & 1) ? 0x42BE44B0u : 0x42DC4480u;
        const uint32_t mfin = 0x3CCFC177u;
        const uint32_t blo = mlo ? 0u : big, bhi = mhi ? 0u : big;
        const uint32_t flo = mlo ? mfin : fn, fhi = mhi ? mfin : fn;
        const uint4 z = make_uint4(0, 0, 0, 0);
#pragma unroll
        for (int p = 0; p < 2; p++) {
            uint8_t* bp = smem + SM_BUF + (wg * 2 + p) * BUF + t * 16;
            if (t < 112) {
                *(uint4*)(bp + OFF_K + 2 * COL) = make_uint4(blo, bhi, blo, bhi);
                *(uint4*)(bp + OFF_K + 3 * COL) = make_uint4(blo, bhi, flo, fhi);
                *(uint4*)(bp + OFF_V + 2 * COL) = make_uint4(one, one, one, one);
                if (t >= F) {
                    *(uint4*)(bp + OFF_K) = z;
                    *(uint4*)(bp + OFF_K + COL) = z;
                    *(uint4*)(bp + OFF_V) = z;
                    *(uint4*)(bp + OFF_V + COL) = z;
                }
            }
        }
    }
    if (io_warp && elect() && wg + NWG < nb) load_item(sb + SM_E + (wg + NWG) * EB, eg + (wg + NWG) * EB, bar + 8);
    if (tid < 256) {
        const int a = tid >> 6, i = (tid & 63) * 4;
        const int d = a == 3 ? i >> 4 : (i >> 3) & 15;
        const int h = a == 3 ? (i >> 3) & 1 : i >> 7, c0 = i & 4;
#pragma unroll
        for (int j = 0; j < 4; j++) {
            float v = __uint_as_float(j & 1 ? (j & 2 ? wreg.y : wreg.x) & 0xFFFF0000u : (j & 2 ? wreg.y : wreg.x) << 16);
            if (a == 2) v *= QSCALE;
            const int n = a == 0 ? c0 * 2 + (j >> 1) * 4 + h * 2 + (j & 1) : a * 16 + h * 8 + c0 + j;
            *(__nv_bfloat16*)(smem + SM_W + (d >> 3) * 1024 + n * 16 + (d & 7) * 2) = __float2bfloat16(v);
        }
    }
    asm volatile("fence.proxy.async.shared::cta;" ::: "memory");
    __syncthreads();
    PROF_MARK(1);

    const int g = lane >> 2, q = lane & 3, r8 = lane & 7, m = lane >> 3;
    State st;
    st.mq = st.mkA = st.mkB = 0;
    if (wg < nb) {
        uint32_t buf = sb + SM_BUF + wg * 2 * BUF, bufo = buf + BUF;
        const uint32_t scr = buf + OFF_O + (tid & 127) * 4;
        const int row0 = 16 * w + r8 + (m & 1) * 8;
        const int row1 = (m & 1) ? 96 + (r8 & 3) : 64 + 8 * w + r8;
        const uint32_t oE0 = keep(row0 * 32 + (m >> 1) * 16, scr), oE1 = keep(row1 * 32 + (m >> 1) * 16, scr);
        const uint32_t oEC = keep((64 + 8 * w + r8) * 32 + (m & 1) * 16, scr);
        const uint32_t oK0 = keep((m >> 1) * COL + row0 * 16, scr), oK1 = keep((m >> 1) * COL + row1 * 16, scr);
        const uint32_t barid = keep(wg + 1, scr);
        uint32_t augc[6];
#pragma unroll
        for (int i = 0; i < 6; i++) augc[i] = ldc(sb + SM_C + lane * 4);
        const uint32_t metaAB = ldc(sb + SM_C + 128 + lane * 4);
        const uint32_t metaC = ldc(sb + SM_C + 256 + lane * 4);
        const uint32_t one2 = ldc(sb + SM_C + 384 + lane * 4);
        const uint64_t dW = mkdesc(sb + SM_W, 1024, 128);
        const uint32_t bx = buf ^ bufo;
        uint32_t kLo = (uint32_t)mkdesc(buf + OFF_K, COL, 0), vLo = (uint32_t)mkdesc(buf + OFF_V, 128, 0);
        const uint32_t kX = kLo ^ (kLo + (BUF >> 4)), vX = vLo ^ (vLo + (BUF >> 4));
        uint32_t eN = sb + SM_E + wg * EB;
        const uint32_t eLast = eN + (nb - 1 - wg) / NWG * (NWG * EB);
        uint32_t barN = bar, phN = 0;
        const bool st_warp = w == ((wg + 2) & 3);

        float sa[24], sbb[28];
        uint32_t pa[12], pb[16], a0[4], a1[4];
        pb[14] = keep(0, scr); pb[15] = keep(0, scr);
#define ZPB()
#define QKA(SEL, Q, I, M) qk48<SEL>(sa, st.Q[0], st.Q[1], augc[I], augc[I + 1], dK, M)
#define QKB(SEL, Q, I, M) qk56<SEL>(sbb, st.Q[0], st.Q[1], augc[I], augc[I + 1], dK + 48, M)
#define PVA(N, O, D) pv<N, true>(O, pa, D); pv<N, false>(O, pa + 4, D + 16); pv<N, false>(O, pa + 8, D + 32)
#define PVB(N, O, D) pv<N, false>(O, pb, D + 48); pv<N, false>(O, pb + 4, D + 64); pv<N, false>(O, pb + 8, D + 80); pv<N, false>(O, pb + 12, D + 96)
#define EXPA() exp_block<0, 12>(sa, pa, one2, sh16); pin<12>(pa)
#define EXPB() exp_block<12, 14>(sbb, pb, one2, sh16); ZPB(); pin<16>(pb)
        {
            float d0[32], d1[32];
            mbar_wait(bar, 0);
            PROF_MARK(2);
            ldsm4(a0, eN + oE0);
            ldsm4(a1, eN + oE1);
            WG_ARRIVE();
            proj64(d0, a0, dW);
            proj64(d1, a1, dW);
            WG_COMMIT();
            WG_WAIT(0);
            pin<32>(d0); pin<32>(d1);
            cvt_kv(st, d0, buf + oK0);
            cvt_kv(st, d1, buf + oK1);
            cvt_qr0(st, d0 + 16);
            cvt_qr1(st, d1 + 16);
        }
        const uint8_t* gio = st_warp ? og + (wg - NWG) * EB : eg + (wg + 2 * NWG) * EB;
        bool first = true, last;
#pragma unroll 1
        do {
            PROF_MARK(3 + phN);
            if (st_warp) asm volatile("cp.async.bulk.wait_group.read 0;" ::: "memory");
            asm volatile("fence.proxy.async.shared::cta;" ::: "memory");
            asm volatile("bar.sync %0, 128;" ::"r"(barid) : "memory");
            const uint64_t dK = desc64(kLo, 8), dVA = desc64(vLo, 2 * COL >> 4), dV = desc64(vLo, COL >> 4);
            const uint64_t dVB = dV + (COL >> 4);
            float oA[8], oB[8], oC[12];
            WG_ARRIVE();
            QKA(0, qA, 0, metaAB);
            WG_COMMIT();
            QKB(0, qA, 0, metaAB);
            WG_COMMIT();
            if (st_warp) {
                if (!first && elect()) store_item((void*)gio, bufo + OFF_O);
            } else if (io_warp) {
                if (eN + 2 * NWG * EB <= eLast && elect()) load_item(eN + 2 * NWG * EB, gio, barN);
            }
            gio += NWG * EB;
            first = false;
            WG_WAIT(1);
            pin<24>(sa);
            EXPA();
            WG_ARRIVE();
            QKA(1, qB, 2, metaAB);
            PVA(16, oA, dVA);
            WG_COMMIT();
            WG_WAIT(1);
            pin<28>(sbb);
            EXPB();
            WG_ARRIVE();
            QKB(1, qB, 2, metaAB);
            PVB(16, oA, dVA);
            WG_COMMIT();
            WG_WAIT(1);
            pin<24>(sa);
            EXPA();
            WG_ARRIVE();
            QKA(0, qC, 4, metaC);
            PVA(16, oB, dVB);
            WG_COMMIT();
            WG_WAIT(1);
            pin<28>(sbb); pin<8>(oA);
            const uint32_t yA0 = fin(oA[0], oA[1], oA[4], st.r[0]), yA1 = fin(oA[2], oA[3], oA[6], st.r[1]);
            EXPB();
            WG_ARRIVE();
            QKB(0, qC, 4, metaC);
            PVB(16, oB, dVB);
            WG_COMMIT();
            last = eN == eLast;
            if (!last) {
                eN += NWG * EB; barN ^= 8; phN++;
                mbar_wait(barN, (phN >> 1) & 1);
            }
            ldsm4(a0, eN + oE0);
            ldsm4(a1, eN + oE1);
            WG_WAIT(1);
            pin<24>(sa);
            EXPA();
            float d0[32], d1[32];
            WG_ARRIVE();
            proj64(d0, a0, dW);
            PVA(24, oC, dV);
            WG_COMMIT();
            WG_WAIT(1);
            pin<28>(sbb); pin<8>(oB);
            stsm4(buf + OFF_O + oE0, yA0, yA1, fin(oB[0], oB[1], oB[4], st.r[2]), fin(oB[2], oB[3], oB[6], st.r[3]));
            EXPB();
            WG_ARRIVE();
            proj64(d1, a1, dW);
            PVB(24, oC, dV);
            WG_COMMIT();
            WG_WAIT(1);
            pin<32>(d0);
            cvt_kv(st, d0, bufo + oK0);
            cvt_qr0(st, d0 + 16);
            WG_WAIT(0);
            pin<32>(d1); pin<12>(oC);
            cvt_kv(st, d1, bufo + oK1);
            stsm2(buf + OFF_O + oEC, fin(oC[0], oC[1], oC[8], st.r[4]), fin(oC[6], oC[7], oC[10], st.r[5]));
            cvt_qr1(st, d1 + 16);
            buf ^= bx; bufo ^= bx; kLo ^= kX; vLo ^= vX;
        } while (!last);
        PROF_MARK(30);
        asm volatile("fence.proxy.async.shared::cta;" ::: "memory");
        asm volatile("bar.sync %0, 128;" ::"r"(barid) : "memory");
        if (st_warp && elect()) store_item((void*)gio, bufo + OFF_O);
    }
    {
        uint32_t wqf[4], wvf[4], wrf[4], wkf[4];
        const uint32_t aW = sb + SM_W + (m & 1) * 1024 + ((m >> 1) * 8 + r8) * 16;
        ldsm4(wqf, aW + 512);
        ldsm4(wvf, aW + 256);
        ldsm4(wrf, aW + 768);
#pragma unroll
        for (int i = 0; i < 4; i++) wkf[i] = __ldg((const uint32_t*)wk + (i & 1) * 64 + ((i >> 1) * 8 + g) * 4 + q);
        const uint32_t oB = (r8 + (m >> 1) * 8) * 32 + (m & 1) * 16;
        const uint32_t oBt = (96 + (r8 & 3)) * 32 + (m & 1) * 16;
        const bool lo = g < 4;
        for (int lb = wg + w * NWG; lb < nb; lb += 4 * NWG) {
            const uint32_t eb = sb + SM_E + lb * EB;
            uint32_t et[4];
            ldsm4(et, eb + oBt);
            float t0[4] = {0, 0, 0, 0}, t1[4] = {0, 0, 0, 0};
            mma16(t0, et[0], 0, et[1], 0, wqf[0], wqf[1]);
            mma16(t1, et[0], 0, et[1], 0, wqf[2], wqf[3]);
            const uint32_t q0 = lo ? pack(t0[0], t0[1]) : 0u, q1 = lo ? 0u : pack(t1[0], t1[1]);
            st.mq = amax2(st.mq, q0 | q1);
            float u0[4] = {0, 0, 0, 0}, u1[4] = {0, 0, 0, 0};
            mma16(u0, q0, 0, q1, 0, wkf[0], wkf[1]);
            mma16(u1, q0, 0, q1, 0, wkf[2], wkf[3]);
            const uint32_t ua = pack(u0[0], u0[1]), ub = pack(u1[0], u1[1]);
            float o[4] = {0, 0, 0, 0}, l[4] = {0, 0, 0, 0};
#pragma unroll
            for (int t = 0; t < 7; t++) {
                uint32_t b[4], a[4], p0, p1;
                float s0[4] = {0, 0, 0, 0}, s1[4] = {0, 0, 0, 0};
                if (t < 6) {
                    ldsm4(b, eb + t * 512 + oB);
                    ldsm4t(a, eb + t * 512 + oB);
                    mma16(s0, ua, 0, ub, 0, b[0], b[1]);
                    mma16(s1, ua, 0, ub, 0, b[2], b[3]);
                    p0 = pack(ex2(s0[0]), ex2(s0[1]));
                    p1 = pack(ex2(s1[0]), ex2(s1[1]));
                } else {
                    ldsm4t(a, eb + oBt);
                    mma16(s0, ua, 0, ub, 0, et[0], et[1]);
                    p0 = q < 2 ? pack(ex2(s0[0]), ex2(s0[1])) : 0u;
                    p1 = 0;
                }
                mma16(o, a[0], a[1], a[2], a[3], p0, p1);
                mma16(l, 0x3F803F80u, 0x3F803F80u, 0x3F803F80u, 0x3F803F80u, p0, p1);
            }
            const float i0 = rcp(l[0]), i1 = rcp(l[1]);
            const uint32_t ca = movm(pack(o[0] * i0, o[1] * i1)), cb = movm(pack(o[2] * i0, o[3] * i1));
            float y0[4] = {0, 0, 0, 0}, y1[4] = {0, 0, 0, 0};
            mma16(y0, et[0], 0, et[1], 0, wrf[0], wrf[1]);
            mma16(y1, et[0], 0, et[1], 0, wrf[2], wrf[3]);
            mma16(y0, ca, 0, cb, 0, wvf[0], wvf[1]);
            mma16(y1, ca, 0, cb, 0, wvf[2], wvf[3]);
            *(uint32_t*)(og + lb * EB + (96 + (g & 3)) * 32 + (g >> 2) * 16 + q * 4) =
                lo ? pack_relu(y0[0], y0[1]) : pack_relu(y1[0], y1[1]);
        }
    }
    PROF_MARK(31);
    {
        float nq, nk;
        {
            const float a = __uint_as_float(st.mq << 16), b = __uint_as_float(st.mq & 0xFFFF0000u);
            nq = a * a + b * b;
            nq += __shfl_xor_sync(0xffffffffu, nq, 1);
            nq += __shfl_xor_sync(0xffffffffu, nq, 2);
            const float c = __uint_as_float(st.mkA << 16), d = __uint_as_float(st.mkA & 0xFFFF0000u);
            const float f = __uint_as_float(st.mkB << 16), h = __uint_as_float(st.mkB & 0xFFFF0000u);
            nk = c * c + d * d + f * f + h * h;
            nk += __shfl_xor_sync(0xffffffffu, nk, 2);
        }
        const uint32_t uq = __reduce_max_sync(0xffffffffu, __float_as_uint(nq) & 0x7FFFFFFFu);
        const uint32_t uk = __reduce_max_sync(0xffffffffu, __float_as_uint(nk) & 0x7FFFFFFFu);
        uint32_t* red = (uint32_t*)(smem + SM_BUF + wg * 2 * BUF);
        if (lane == 0) { red[w] = uq; red[4 + w] = uk; }
        asm volatile("bar.sync %0, 128;" ::"r"(wg + 1) : "memory");
        const float bq = __uint_as_float(max(max(red[0], red[1]), max(red[2], red[3])));
        const float bk = __uint_as_float(max(max(red[4], red[5]), max(red[6], red[7])));
        const bool safe = bq * bk <= SLIMIT * SLIMIT;
        if (safe) {
            asm volatile("cp.async.bulk.wait_group.read 0;" ::: "memory");
            PROF_MARK(32); PROF_GT(1);
        } else {
            asm volatile("cp.async.bulk.wait_group 0;" ::: "memory");
            __threadfence();
            asm volatile("bar.sync %0, 128;" ::"r"(wg + 1) : "memory");
            float* kv = (float*)(smem + SM_BUF + wg * 2 * BUF);
            for (int lb = wg; lb < nb; lb += NWG)
                slow_path(e + (size_t)(b0 + lb) * (F * 16), wq, wk, wv, wr, out + (size_t)(b0 + lb) * (F * 16), kv, tid & 127, wg + 1);
        }
    }
}

}

extern "C" void kernel_launch(void* const* d_in, const int* in_sizes, int n_in, void* d_out, int out_size) {
    static int sms = 0;
    if (!sms) {
        cudaDeviceGetAttribute(&sms, cudaDevAttrMultiProcessorCount, 0);
        cudaFuncSetAttribute(autoint_kernel, cudaFuncAttributeMaxDynamicSharedMemorySize, SM_TOTAL);
    }
    const int B = in_sizes[0] / (F * 16);
    int grid = sms;
    if (grid * MAXB < B) grid = (B + MAXB - 1) / MAXB;
    autoint_kernel<<<grid, NWG * 128, SM_TOTAL>>>(
        (const __nv_bfloat16*)d_in[0], (const __nv_bfloat16*)d_in[1], (const __nv_bfloat16*)d_in[2],
        (const __nv_bfloat16*)d_in[3], (const __nv_bfloat16*)d_in[4], (__nv_bfloat16*)d_out, B / grid, B % grid, 65536u);
}
```

```cpp
#include <cuda_runtime.h>
#include <cuda_bf16.h>
#include <stdint.h>

#define TAIL 1
#define EPI 1
#define MUMASK 0x1041041u
#define TDELAY 0
#define TRK 1
#define REV 1
#define STAG 0
#define EARLY 0
#define PROF_MARK(i)
#define PROF_GT(i)

namespace {

constexpr int NWG = 3;
constexpr int F = 100;
constexpr int EB = 3200;
constexpr int ES = 3232;
constexpr int MAXB = 32;
constexpr int COL = 1792;
constexpr int OFF_K = 0;
constexpr int OFF_V = 4 * COL;
constexpr int BUF = 7 * COL;
constexpr uint32_t SB = 1024;
constexpr int SM_W = NWG * 2 * BUF;
constexpr int SM_E = SM_W + 2560;
constexpr int SM_BAR = SM_E + MAXB * ES;
constexpr int SM_RED = SM_BAR + MAXB * 8;
constexpr int SM_SCR = SM_RED + 256;
constexpr int SM_TOTAL = SM_SCR + 12800;
constexpr uint32_t ONEV = EPI ? 0x3F7F3F7Fu : 0x3F803F80u;

constexpr float QSCALE = 0.35355339059327373f * 1.4426950408889634f;
constexpr float SLIMIT = 100.0f;

__device__ __forceinline__ uint64_t mkdesc(uint32_t addr, uint32_t lbo, uint32_t sbo) {
    return (uint64_t)((addr & 0x3FFFF) >> 4) | ((uint64_t)(lbo >> 4) << 16) | ((uint64_t)(sbo >> 4) << 32);
}
#define WG_ARRIVE() asm volatile("wgmma.fence.sync.aligned;" ::: "memory")
#define WG_COMMIT() asm volatile("wgmma.commit_group.sync.aligned;" ::: "memory")
#define WG_WAIT(n) asm volatile("wgmma.wait_group.sync.aligned " #n ";" ::: "memory")
template <int N> __device__ __forceinline__ void pin(float* d) {
#pragma unroll
    for (int i = 0; i < N; i++) asm volatile("" : "+f"(d[i])::"memory");
}
template <int N> __device__ __forceinline__ void pin(uint32_t* d) {
#pragma unroll
    for (int i = 0; i < N; i++) asm volatile("" : "+r"(d[i])::"memory");
}
#define O4(c, d, i) c(d[i]), c(d[i + 1]), c(d[i + 2]), c(d[i + 3])
#define O8(c, d, i) O4(c, d, i), O4(c, d, i + 4)

template <int SEL>
__device__ __forceinline__ void qk48(float* d, const uint32_t* a, uint64_t b, uint32_t meta) {
    asm volatile("wgmma.mma_async.sp.sync.aligned.m64n48k32.f32.bf16.bf16 "
                 "{%0,%1,%2,%3,%4,%5,%6,%7,%8,%9,%10,%11,%12,%13,%14,%15,%16,%17,%18,%19,%20,%21,%22,%23},"
                 "{%24,%25,%26,%27}, %28, %29, %30, 0, 1, 1, 0;"
                 : O8("=f", d, 0), O8("=f", d, 8), O8("=f", d, 16)
                 : "r"(a[0]), "r"(a[1]), "r"(a[2]), "r"(a[3]), "l"(b), "r"(meta), "n"(SEL));
}
template <int SEL>
__device__ __forceinline__ void qk56(float* d, const uint32_t* a, uint64_t b, uint32_t meta) {
    asm volatile("wgmma.mma_async.sp.sync.aligned.m64n56k32.f32.bf16.bf16 "
                 "{%0,%1,%2,%3,%4,%5,%6,%7,%8,%9,%10,%11,%12,%13,%14,%15,%16,%17,%18,%19,%20,%21,%22,%23,%24,%25,%26,%27},"
                 "{%28,%29,%30,%31}, %32, %33, %34, 0, 1, 1, 0;"
                 : O8("=f", d, 0), O8("=f", d, 8), O8("=f", d, 16), O4("=f", d, 24)
                 : "r"(a[0]), "r"(a[1]), "r"(a[2]), "r"(a[3]), "l"(b), "r"(meta), "n"(SEL));
}
__device__ __forceinline__ void proj64(float* d, const uint32_t* a, uint64_t b) {
    asm volatile("wgmma.mma_async.sync.aligned.m64n64k16.f32.bf16.bf16 "
                 "{%0,%1,%2,%3,%4,%5,%6,%7,%8,%9,%10,%11,%12,%13,%14,%15,%16,%17,%18,%19,%20,%21,%22,%23,%24,%25,%26,%27,%28,%29,%30,%31},"
                 "{%32,%33,%34,%35}, %36, 0, 1, 1, 1;"
                 : O8("=f", d, 0), O8("=f", d, 8), O8("=f", d, 16), O8("=f", d, 24)
                 : "r"(a[0]), "r"(a[1]), "r"(a[2]), "r"(a[3]), "l"(b));
}
template <int N, bool FIRST> __device__ __forceinline__ void pv(float* d, const uint32_t* a, uint64_t b) {
    if (N == 16 && FIRST)
        asm volatile("wgmma.mma_async.sync.aligned.m64n16k16.f32.bf16.bf16 {%0,%1,%2,%3,%4,%5,%6,%7},{%8,%9,%10,%11}, %12, 0, 1, 1, 1;"
                     : O8("=f", d, 0) : "r"(a[0]), "r"(a[1]), "r"(a[2]), "r"(a[3]), "l"(b));
    if (N == 16 && !FIRST)
        asm volatile("wgmma.mma_async.sync.aligned.m64n16k16.f32.bf16.bf16 {%0,%1,%2,%3,%4,%5,%6,%7},{%8,%9,%10,%11}, %12, 1, 1, 1, 1;"
                     : O8("+f", d, 0) : "r"(a[0]), "r"(a[1]), "r"(a[2]), "r"(a[3]), "l"(b));
    if (N == 24 && FIRST)
        asm volatile("wgmma.mma_async.sync.aligned.m64n24k16.f32.bf16.bf16 {%0,%1,%2,%3,%4,%5,%6,%7,%8,%9,%10,%11},{%12,%13,%14,%15}, %16, 0, 1, 1, 1;"
                     : O8("=f", d, 0), O4("=f", d, 8) : "r"(a[0]), "r"(a[1]), "r"(a[2]), "r"(a[3]), "l"(b));
    if (N == 24 && !FIRST)
        asm volatile("wgmma.mma_async.sync.aligned.m64n24k16.f32.bf16.bf16 {%0,%1,%2,%3,%4,%5,%6,%7,%8,%9,%10,%11},{%12,%13,%14,%15}, %16, 1, 1, 1, 1;"
                     : O8("+f", d, 0), O4("+f", d, 8) : "r"(a[0]), "r"(a[1]), "r"(a[2]), "r"(a[3]), "l"(b));
}
__device__ __forceinline__ void mma16(float* d, uint32_t a0, uint32_t a1, uint32_t a2, uint32_t a3, uint32_t b0, uint32_t b1) {
    asm("mma.sync.aligned.m16n8k16.row.col.f32.bf16.bf16.f32 {%0,%1,%2,%3},{%4,%5,%6,%7},{%8,%9},{%0,%1,%2,%3};"
        : O4("+f", d, 0) : "r"(a0), "r"(a1), "r"(a2), "r"(a3), "r"(b0), "r"(b1));
}
__device__ __forceinline__ uint32_t pack(float lo, float hi) {
    uint32_t p; asm("cvt.rn.bf16x2.f32 %0, %1, %2;" : "=r"(p) : "f"(hi), "f"(lo)); return p;
}
__device__ __forceinline__ uint32_t pack_relu(float lo, float hi) {
    uint32_t p; asm("cvt.rn.relu.bf16x2.f32 %0, %1, %2;" : "=r"(p) : "f"(hi), "f"(lo)); return p;
}
__device__ __forceinline__ float ex2(float x) { float y; asm("ex2.approx.ftz.f32 %0, %1;" : "=f"(y) : "f"(x)); return y; }
__device__ __forceinline__ float rcp(float x) { float y; asm("rcp.approx.ftz.f32 %0, %1;" : "=f"(y) : "f"(x)); return y; }
__device__ __forceinline__ uint32_t amax2(uint32_t a, uint32_t b) {
    uint32_t d; asm("max.NaN.xorsign.abs.bf16x2 %0, %1, %2;" : "=r"(d) : "r"(a), "r"(b)); return d;
}
__device__ __forceinline__ uint32_t exp2_pair(float x0, float x1, uint32_t one2, uint32_t sh16) {
    uint32_t z, g, p;
    asm("mad.lo.u32 %0, %1, %2, %3;" : "=r"(z) : "r"(__float_as_uint(x1)), "r"(sh16), "r"(__float_as_uint(x0)));
    asm("lop3.b32 %0, %1, 0x007F007F, %2, 0xEA;" : "=r"(g) : "r"(z), "r"(one2));
    asm("fma.rn.bf16x2 %0, %1, %1, %2;" : "=r"(p) : "r"(g), "r"(0x40014001u));
    return p + z - g;
}
template <int T0, int NP> __device__ __forceinline__ void exp_block(const float* s, uint32_t* p, uint32_t one2, uint32_t sh16) {
#pragma unroll
    for (int i = 0; i < NP; i++) {
        if ((MUMASK >> (T0 + i)) & 1) p[i] = pack(ex2(s[2 * i]), ex2(s[2 * i + 1]));
        else p[i] = exp2_pair(s[2 * i], s[2 * i + 1], one2, sh16);
    }
}
__device__ __forceinline__ void ldsm4(uint32_t* r, uint32_t addr) {
    asm volatile("ldmatrix.sync.aligned.m8n8.x4.shared.b16 {%0,%1,%2,%3}, [%4];"
                 : "=r"(r[0]), "=r"(r[1]), "=r"(r[2]), "=r"(r[3]) : "r"(addr) : "memory");
}
__device__ __forceinline__ void ldsm4t(uint32_t* r, uint32_t addr) {
    asm volatile("ldmatrix.sync.aligned.m8n8.x4.trans.shared.b16 {%0,%1,%2,%3}, [%4];"
                 : "=r"(r[0]), "=r"(r[1]), "=r"(r[2]), "=r"(r[3]) : "r"(addr) : "memory");
}
__device__ __forceinline__ void stsm4(uint32_t addr, uint32_t a, uint32_t b, uint32_t c, uint32_t d) {
    asm volatile("stmatrix.sync.aligned.m8n8.x4.shared.b16 [%0], {%1,%2,%3,%4};" ::"r"(addr), "r"(a), "r"(b), "r"(c), "r"(d) : "memory");
}
__device__ __forceinline__ void ldsm2(uint32_t* r, uint32_t addr) {
    asm volatile("ldmatrix.sync.aligned.m8n8.x2.shared.b16 {%0,%1}, [%2];" : "=r"(r[0]), "=r"(r[1]) : "r"(addr) : "memory");
}
__device__ __forceinline__ uint32_t movm(uint32_t a) {
    uint32_t d; asm volatile("movmatrix.sync.aligned.m8n8.trans.b16 %0, %1;" : "=r"(d) : "r"(a)); return d;
}
__device__ __forceinline__ void mbar_wait(uint32_t bar, uint32_t phase) {
    asm volatile("{.reg .pred p; .reg .b32 c;\n"
                 "mbarrier.try_wait.parity.shared::cta.b64 p, [%0], %1;\n"
                 "@p bra.uni DONE;\n"
                 "mov.b32 c, 0;\n"
                 "LOOP:\n"
                 "mbarrier.try_wait.parity.shared::cta.b64 p, [%0], %1, 1000;\n"
                 "@p bra.uni DONE;\n"
                 "add.u32 c, c, 1;\n"
                 "setp.lt.u32 p, c, 20000;\n"
                 "@p bra.uni LOOP;\n"
                 "DONE:}" ::"r"(bar), "r"(phase) : "memory");
}
__device__ __forceinline__ void mbar_init(uint32_t bar, int n) {
    asm volatile("mbarrier.init.shared::cta.b64 [%0], %1;" ::"r"(bar), "r"(n) : "memory");
}
__device__ __forceinline__ void load_item(uint32_t dst, const uint8_t* src, uint32_t bar) {
    asm volatile("mbarrier.arrive.expect_tx.shared::cta.b64 _, [%0], %1;" ::"r"(bar), "n"(EB) : "memory");
    asm volatile("cp.async.bulk.shared::cluster.global.mbarrier::complete_tx::bytes [%0], [%1], 1664, [%2];"
                 ::"r"(dst), "l"(src), "r"(bar) : "memory");
    asm volatile("cp.async.bulk.shared::cluster.global.mbarrier::complete_tx::bytes [%0], [%1], 1536, [%2];"
                 ::"r"(dst + 1680), "l"(src + 1664), "r"(bar) : "memory");
}
__device__ __forceinline__ bool elect() {
    uint32_t p;
    asm volatile("{.reg .pred p; elect.sync _|p, 0xffffffff; selp.u32 %0, 1, 0, p;}" : "=r"(p));
    return p;
}
__device__ __forceinline__ void keep4(uint32_t* v, uint32_t scratch) {
    asm volatile("st.volatile.shared.v4.b32 [%4], {%0,%1,%2,%3};\nld.volatile.shared.v4.b32 {%0,%1,%2,%3}, [%4];"
                 : "+r"(v[0]), "+r"(v[1]), "+r"(v[2]), "+r"(v[3]) : "r"(scratch) : "memory");
}
__device__ __forceinline__ uint64_t desc64(uint32_t lo, uint32_t hi) {
    uint64_t d; asm("mov.b64 %0, {%1, %2};" : "=l"(d) : "r"(lo), "r"(hi)); return d;
}
__device__ __forceinline__ uint32_t add_relu(uint32_t a, uint32_t b) {
    uint32_t d; asm("fma.rn.relu.bf16x2 %0, %1, %2, %3;" : "=r"(d) : "r"(a), "r"(0x3F803F80u), "r"(b)); return d;
}
__device__ __forceinline__ uint32_t fin(float o0, float o1, float l, uint32_t r) {
    const float i = rcp(l);
    uint32_t d;
    asm("{.reg .b16 lo, hi; .reg .b32 t; mov.b32 {lo, hi}, %2; mov.b32 t, {hi, hi}; fma.rn.relu.bf16x2 %0, %1, t, %3;}"
        : "=r"(d) : "r"(pack(o0, o1)), "r"(__float_as_uint(i)), "r"(r));
    return d;
}
__device__ __forceinline__ float bfr(float x) { return __bfloat162float(__float2bfloat16(x)); }

__device__ __forceinline__ void slow_proj(float* y, const __nv_bfloat16* x, const __nv_bfloat16* w, int ld) {
#pragma unroll
    for (int c = 0; c < 8; c++) y[c] = 0.f;
#pragma unroll 1
    for (int d = 0; d < 16; d++) {
        const float xv = __bfloat162float(x[d]);
        const uint4 wv = *(const uint4*)(w + d * ld);
        const uint32_t ww[4] = {wv.x, wv.y, wv.z, wv.w};
#pragma unroll
        for (int c = 0; c < 8; c++) y[c] = fmaf(xv, __uint_as_float(c & 1 ? ww[c >> 1] & 0xFFFF0000u : ww[c >> 1] << 16), y[c]);
    }
#pragma unroll
    for (int c = 0; c < 8; c++) y[c] = bfr(y[c]);
}
__device__ __forceinline__ void slow_path(const __nv_bfloat16* e, const __nv_bfloat16* wq, const __nv_bfloat16* wk,
                                          const __nv_bfloat16* wv, const __nv_bfloat16* wr, __nv_bfloat16* out,
                                          float* kv, int t, int barid, bool leftover) {
    float a[8], q[8];
    e += t * 16;
    if (t < F) {
#pragma unroll 1
        for (int i = 0; i < 4; i++) {
            slow_proj(a, e, (i & 2 ? wv : wk) + (i & 1) * 128, 8);
#pragma unroll
            for (int c = 0; c < 8; c++) kv[t * 32 + i * 8 + c] = a[c];
        }
    }
    asm volatile("bar.sync %0, 128;" ::"r"(barid) : "memory");
    if (t < F && ((t >> 2) == 12) == leftover) {
#pragma unroll 1
        for (int h = 0; h < 2; h++) {
            slow_proj(q, e, wq + h * 128, 8);
#pragma unroll
            for (int c = 0; c < 8; c++) a[c] = 0.f;
            float m = -INFINITY, l = 0.f;
#pragma unroll 1
            for (int i = 0; i < 3 * F; i++) {
                const int pass = i / F;
                const float* kj = kv + (i - pass * F) * 32 + h * 8;
                float s = 0.f;
#pragma unroll
                for (int c = 0; c < 8; c++) s = fmaf(q[c], kj[c], s);
                s = bfr(bfr(s) * 0.35355339059327373f);
                if (pass == 0) m = fmaxf(m, s);
                else {
                    const float p = __expf(s - m);
                    if (pass == 1) l += p;
                    else {
                        const float pn = bfr(__fdividef(p, l));
#pragma unroll
                        for (int c = 0; c < 8; c++) a[c] = fmaf(pn, kj[16 + c], a[c]);
                    }
                }
            }
            slow_proj(q, e, wr + h * 8, 16);
#pragma unroll
            for (int c = 0; c < 8; c++) {
                const float o = bfr(bfr(a[c]) + q[c]);
                out[t * 16 + h * 8 + c] = __float2bfloat16(o > 0.f ? o : o * 0.f);
            }
        }
    }
    asm volatile("bar.sync %0, 128;" ::"r"(barid) : "memory");
}
__device__ __forceinline__ uint32_t hsq(uint32_t a) {
    uint32_t d; asm("mul.rn.bf16x2 %0, %1, %1;" : "=r"(d) : "r"(a)); return d;
}
__device__ __forceinline__ uint32_t hsqa(uint32_t a, uint32_t c) {
    uint32_t d; asm("fma.rn.bf16x2 %0, %1, %1, %2;" : "=r"(d) : "r"(a), "r"(c)); return d;
}
__device__ __forceinline__ uint32_t hmax(uint32_t a, uint32_t b) {
    uint32_t d; asm("max.NaN.bf16x2 %0, %1, %2;" : "=r"(d) : "r"(a), "r"(b)); return d;
}
__device__ __forceinline__ uint32_t hadd2(uint32_t a, uint32_t b) {
    uint32_t d; asm("add.rn.bf16x2 %0, %1, %2;" : "=r"(d) : "r"(a), "r"(b)); return d;
}
__device__ __forceinline__ void mma16z(float* d, const uint32_t* a, uint32_t b0, uint32_t b1) {
    asm("mma.sync.aligned.m16n8k16.row.col.f32.bf16.bf16.f32 {%0,%1,%2,%3},{%4,%5,%6,%7},{%8,%9},{%10,%10,%10,%10};"
        : O4("=f", d, 0) : "r"(a[0]), "r"(a[1]), "r"(a[2]), "r"(a[3]), "r"(b0), "r"(b1), "f"(0.f));
}
__device__ __forceinline__ void lds2v(uint32_t* v, uint32_t addr) {
    asm volatile("ld.volatile.shared.v2.b32 {%0,%1}, [%2];" : "=r"(v[0]), "=r"(v[1]) : "r"(addr));
}
__device__ __forceinline__ bool wg_any(bool p, int barid) {
    uint32_t r;
    asm volatile("{.reg .pred p, q; setp.ne.u32 p, %1, 0; bar.red.or.pred q, %2, 128, p; selp.u32 %0, 1, 0, q;}"
                 : "=r"(r) : "r"((uint32_t)p), "r"(barid) : "memory");
    return r;
}

__device__ __forceinline__ void load_pair(const uint8_t* eg, const uint8_t* egx, int la, int nb, int nl) {
    if (elect()) {
        if (la < nl) load_item(SB + SM_E + la * ES, eg + la * EB, SB + SM_BAR + la * 8);
        if (la + 1 < nl) load_item(SB + SM_E + (la + 1) * ES, la + 1 < nb ? eg + (la + 1) * EB : egx, SB + SM_BAR + la * 8 + 8);
    }
}
__device__ __forceinline__ bool tail_phase(const uint8_t* eg, const uint8_t* egx, uint8_t* og, uint8_t* ogx, int nb, int nt, bool skip,
                                           int w, int lane, uint32_t scr) {
    const int g = lane >> 2, q = lane & 3, r8 = lane & 7, m = lane >> 3;
    uint32_t ad[4] = {SB + SM_W + lane * 16u, (r8 & 3) * 32u + (r8 >> 2) * 1680 + (m >> 1) * 128 + (m & 1) * 16,
                      (48 + (r8 & 3)) * 32u + (m & 1) * 16, (48 + (g & 3)) * 32u + (g >> 2) * 16 + q * 4};
    keep4(ad, scr);
    const uint32_t aW = ad[0], oB = ad[1], oT = ad[2], oO = ad[3];
    const bool lo = g < 4;
    uint32_t lmin = 0x3F800000u, lmax = 0x3F800000u;
#pragma unroll 1
    for (int la = 2 * w; la < nt; la += 8) {
        const int d1 = la + 1 < nt;
        const uint32_t ea = SB + SM_E + la * ES, dE = d1 * ES;
        const uint32_t aT = ea + (oT & ~16u) + (m & 1) * dE + (m >> 1) * 16;
        mbar_wait(SB + SM_BAR + la * 8, 0);
        mbar_wait(SB + SM_BAR + (la + d1) * 8, 0);
        load_pair(eg, egx, la + 8, nb, nt);
        if (skip) continue;
        if (TDELAY && la < 8) __nanosleep(TDELAY);
        uint32_t et[4], wf[4], u[4];
        float t0[4], t1[4];
        ldsm4(et, aT);
        ldsm4t(wf, aW + 1024);
        mma16z(t0, et, wf[0], wf[1]);
        mma16z(t1, et, wf[2], wf[3]);
        ldsm4(wf, aW + 2048);
        et[0] = lo ? pack(t0[0], t0[1]) : 0u;
        et[1] = lo ? pack(t0[2], t0[3]) : 0u;
        et[2] = lo ? 0u : pack(t1[0], t1[1]);
        et[3] = lo ? 0u : pack(t1[2], t1[3]);
        mma16z(t0, et, wf[0], wf[1]);
        mma16z(t1, et, wf[2], wf[3]);
        u[0] = pack(t0[0], t0[1]); u[1] = pack(t0[2], t0[3]); u[2] = pack(t1[0], t1[1]); u[3] = pack(t1[2], t1[3]);
        uint32_t eb = ea;
#pragma unroll 1
        for (int it = 0; it < 2; it++, eb += dE) {
            float o[4], l[4];
            uint32_t s0, s1, h0, h1;
#pragma unroll
            for (int t = 0; t < 7; t++) {
                uint32_t b[4], a[4], p0, p1 = 0;
                if (t < 6) ldsm4(b, eb + t * 256 + oB); else ldsm2(b, eb + oT);
                ldsm4t(a, t < 6 ? eb + t * 256 + oB : eb + oT);
                mma16z(t0, u, b[0], b[1]);
                if (t < 6) mma16z(t1, u, b[2], b[3]);
                p0 = pack(ex2(t0[0]), ex2(t0[1]));
                if (t < 6) p1 = pack(ex2(t1[0]), ex2(t1[1]));
                else if (q >= 2) p0 = 0;
                if (t == 0) mma16z(o, a, p0, p1); else mma16(o, a[0], a[1], a[2], a[3], p0, p1);
                if (t == 6) s0 = hadd2(s0, p0);
                else if (!(t & 1)) { h0 = p0; h1 = p1; }
                else if (t == 1) { s0 = hadd2(h0, p0); s1 = hadd2(h1, p1); }
                else { s0 = hadd2(s0, hadd2(h0, p0)); s1 = hadd2(s1, hadd2(h1, p1)); }
            }
            asm volatile("ld.volatile.shared.v4.b32 {%0,%1,%2,%3}, [%4];" : "=r"(wf[0]), "=r"(wf[1]), "=r"(wf[2]), "=r"(wf[3]) : "r"(SB + SM_RED + 128));
            mma16z(l, wf, s0, s1);
            lmin = min(min(lmin, __float_as_uint(l[0])), __float_as_uint(l[1]));
            lmax = max(max(lmax, __float_as_uint(l[0])), __float_as_uint(l[1]));
            const float i0 = rcp(l[0]), i1 = rcp(l[1]);
            et[0] = et[1]; et[2] = et[3];
            et[1] = movm(pack(o[0] * i0, o[1] * i1));
            et[3] = movm(pack(o[2] * i0, o[3] * i1));
            u[0] = u[1]; u[2] = u[3];
        }
        ldsm4t(wf, aW + 512);
        mma16z(t0, et, wf[0], wf[1]);
        mma16z(t1, et, wf[2], wf[3]);
        ldsm4(et, aT);
        ldsm4t(wf, aW + 1536);
        mma16(t0, et[0], et[1], et[2], et[3], wf[0], wf[1]);
        mma16(t1, et[0], et[1], et[2], et[3], wf[2], wf[3]);
        *(uint32_t*)(og + la * EB + oO) = lo ? pack_relu(t0[0], t0[1]) : pack_relu(t1[0], t1[1]);
        *(uint32_t*)((la + d1 < nb ? og + (la + d1) * EB : ogx) + oO) = lo ? pack_relu(t0[2], t0[3]) : pack_relu(t1[2], t1[3]);
    }
    return lmin < (27u << 23) || lmax > (227u << 23);
}

struct State {
    uint32_t qA[4], qB[4], qC[4];
    uint32_t r[6];
    uint32_t mq, mkA, mkB;
};
__device__ __forceinline__ void cvt_kv(State& st, const float* x, uint32_t aK) {
    uint32_t k[4];
#pragma unroll
    for (int i = 0; i < 4; i++) k[i] = pack(x[2 * i], x[2 * i + 1]);
    stsm4(aK, k[0], k[1], k[2], k[3]);
    stsm4(aK + OFF_V, pack(x[8], x[9]), pack(x[10], x[11]), pack(x[12], x[13]), pack(x[14], x[15]));
    st.mkA = hmax(st.mkA, hsqa(k[3], hsqa(k[2], hsqa(k[1], hsq(k[0])))));
}
__device__ __forceinline__ void cvt_qr0(State& st, const float* x, uint32_t aAug) {
    lds2v(st.qA + 2, aAug);
    lds2v(st.qB + 2, aAug);
    st.qA[0] = pack(x[0], x[1]);   st.qA[1] = pack(x[2], x[3]);
    st.qB[0] = pack(x[4], x[5]);   st.qB[1] = pack(x[6], x[7]);
#pragma unroll
    for (int i = 0; i < 4; i++) st.r[i] = pack(x[8 + 2 * i], x[9 + 2 * i]);
}
__device__ __forceinline__ void cvt_qr1(State& st, const float* x) {
    st.qC[0] = pack(x[0], x[1]);   st.qC[1] = pack(x[4], x[5]);
    st.r[4] = pack(x[8], x[9]);    st.r[5] = pack(x[12], x[13]);
    st.mq = hmax(hmax(st.mq, hsqa(st.qC[0], hsqa(st.qA[1], hsq(st.qA[0])))), hsqa(st.qC[1], hsqa(st.qB[1], hsq(st.qB[0]))));
}

__global__ void __launch_bounds__(512, 1)
autoint_kernel(const __nv_bfloat16* __restrict__ e, const __nv_bfloat16* __restrict__ wq, const __nv_bfloat16* __restrict__ wk,
               const __nv_bfloat16* __restrict__ wv, const __nv_bfloat16* __restrict__ wr, __nv_bfloat16* __restrict__ out,
               int base, int rem, int moved, uint32_t sh16) {
    extern __shared__ __align__(1024) uint8_t smem[];
    PROF_MARK(0); PROF_GT(0);
    const int tid = threadIdx.x, lane = tid & 31;
    const int wid = __shfl_sync(0xffffffffu, tid >> 5, 0);
    const int wg = wid >> 2, w = wid & 3;
    const int g = lane >> 2, q = lane & 3, r8 = lane & 7, m = lane >> 3;
    const int cta = blockIdx.x;
    const int nb = base + (cta < rem);
    const int b0 = base * cta + min(cta, rem);
    const uint8_t* eg = (const uint8_t*)e + (size_t)b0 * EB;
    const int c = REV ? NWG - 1 - wg : wg;
    const int fx = cta - rem;
    const int nt = nb + (fx >= 0 && fx < moved);
    const uint8_t* egx = (const uint8_t*)e + (size_t)fx * EB;
    const uint32_t orow = (12 * w + (g & 3) + (g >> 2) * 52) * 32 + q * 4;
    uint32_t a0[4], a1[4];
    if (wg == NWG) {
        const uint4 t = __ldg((const uint4*)(w == 0 ? wk : w == 1 ? wv : w == 2 ? wq : wr) + lane);
        a0[0] = t.x; a0[1] = t.y; a0[2] = t.z; a0[3] = t.w;
        if (elect()) {
#pragma unroll
            for (int i = 0; i < 8; i++) mbar_init(SB + SM_BAR + w * 16 + (i >> 1) * 64 + (i & 1) * 8, 1);
            asm volatile("fence.mbarrier_init.release.cluster;" ::: "memory");
        }
    } else {
        const uint32_t* p = (const uint32_t*)(eg + min(c, nb - 1) * EB + orow);
        const uint32_t* pt = (const uint32_t*)(eg + min(c, nb - 1) * EB + (48 + (g & 3)) * 32 + q * 4);
        a0[0] = __ldg(p); a0[1] = __ldg(p + 32); a0[2] = __ldg(p + 4); a0[3] = __ldg(p + 36);
        a1[0] = __ldg(p + 64); a1[1] = __ldg(pt); a1[2] = __ldg(p + 68); a1[3] = __ldg(pt + 4);
    }
    if ((uint32_t)__cvta_generic_to_shared(smem) != SB) __trap();
    uint8_t* og = (uint8_t*)out + (size_t)b0 * EB;
    const uint32_t scr = SB + SM_SCR + tid * 16;
    uint32_t* red = (uint32_t*)(smem + SM_RED);
    if (wg < NWG) {
        const int t = tid & 127;
        const uint32_t one = t < F ? ONEV : 0u;
        const bool mlo = (MUMASK >> (2 * (t >> 3))) & 1, mhi = (MUMASK >> (2 * (t >> 3) + 1)) & 1;
        const uint32_t big = 0x45C045C0u;
        const uint32_t fn = (t & 1) ? 0x42D244B0u : 0x42F04480u;
        const uint32_t mfin = 0x3CCFC0AEu;
        const uint32_t blo = mlo ? 0u : big, bhi = mhi ? 0u : big;
        const uint32_t flo = mlo ? mfin : fn, fhi = mhi ? mfin : fn;
        uint8_t* bp = smem + wg * 2 * BUF + t * 16;
        if (t < 112) {
#pragma unroll
            for (int p = 0; p < 2; p++) {
                *(uint4*)(bp + p * BUF + OFF_K + 2 * COL) = make_uint4(blo, bhi, blo, bhi);
                *(uint4*)(bp + p * BUF + OFF_K + 3 * COL) = make_uint4(blo, bhi, flo, fhi);
                *(uint4*)(bp + p * BUF + OFF_V + 2 * COL) = make_uint4(one, one, one, one);
            }
        }
        *(uint4*)(smem + (wg * 2 + (t >> 6)) * BUF + ((t >> 4 & 1) + (t >> 3 & 4)) * COL + (96 + (t & 15)) * 16) = make_uint4(0, 0, 0, 0);
    }
    uint32_t ad[4], cs[4], c2[4];
    if (wg < NWG) {
        const uint32_t er = (12 * w + (r8 & 3)) * 32 + (r8 >> 2) * 1680 + (m >> 1) * 16;
        const uint32_t kr = (24 * w + r8) * 16 + (m >> 1) * COL;
        ad[0] = er + (m & 1) * 128;
        ad[1] = (m & 1) ? (48 + (r8 & 3)) * 32 + (m >> 1) * 16 : er + 256;
        ad[2] = kr + (m & 1) * 128;
        ad[3] = (m & 1) ? (96 + (r8 & 3)) * 16 + (m >> 1) * COL : kr + 256;
        keep4(ad, scr);
        cs[0] = 0x3F803F80u; cs[1] = wg + 1;
        cs[2] = (q & 1) ? 0xEEEE4444u : (q ? 0xEEEEEEEEu : 0x44444444u);
        cs[3] = 0xEEEE4444u;
        keep4(cs, scr);
        c2[0] = SB + SM_RED + 144 + q * 8;
        c2[1] = orow;
        c2[2] = c2[3] = q < 3 ? 0x3FE03FE0u : 0x3F803F80u;
        keep4(c2, scr);
    } else {
        if (tid < NWG * 128 + 12) red[32 + (tid & 15)] = (tid & 15) < 4 || (tid & 15) >= 10 ? 0x3F803F80u : 0x3FE03FE0u;
        const int d = w == 3 ? lane >> 1 : lane & 15, h = w == 3 ? lane & 1 : lane >> 4;
        ad[0] = SB + SM_W + d * 16 + (w ? (w * 2 + h) * 256 : 2048 + h * 128 + (d >> 3) * 128);
        ad[1] = SB + SM_W + d * 16 + h * 4;
        ad[2] = ad[3] = 0;
        keep4(ad, scr);
        if (EARLY) load_pair(eg, egx, 2 * w, nb, nt);
        if (w == 2) {
#pragma unroll
            for (int j = 0; j < 4; j++) a0[j] = pack(__uint_as_float(a0[j] << 16) * QSCALE, __uint_as_float(a0[j] & 0xFFFF0000u) * QSCALE);
        }
        asm volatile("st.shared.v4.b32 [%0], {%1,%2,%3,%4};" ::"r"(ad[0]), "r"(a0[0]), "r"(a0[1]), "r"(a0[2]), "r"(a0[3]) : "memory");
        if (w == 0) {
#pragma unroll
            for (int j = 0; j < 4; j++) asm volatile("st.shared.b32 [%0], %1;" ::"r"(ad[1] + (j >> 1) * 256 + (j & 1) * 8), "r"(a0[j]) : "memory");
        }
    }
    asm volatile("fence.proxy.async.shared::cta;" ::: "memory");
    __syncthreads();
    PROF_MARK(1);

    if (wg == NWG) {
        asm volatile("setmaxnreg.dec.sync.aligned.u32 56;");
        if (!EARLY) load_pair(eg, egx, 2 * w, nb, nt);
        const bool bad = tail_phase(eg, egx, og, (uint8_t*)out + (size_t)fx * EB, nb, nt, !TAIL || (cta < rem && moved), w, lane, scr);
        if (wg_any(bad, NWG + 1)) {
#pragma unroll 1
            for (int lb = 0; lb < nt; lb++) {
                const size_t o = (size_t)(lb < nb ? b0 + lb : fx) * (F * 16);
                slow_path(e + o, wq, wk, wv, wr, out + o, (float*)(smem + SM_SCR), tid & 127, NWG + 1, true);
            }
        }
        PROF_MARK(32); PROF_GT(1);
    } else {
        asm volatile("setmaxnreg.inc.sync.aligned.u32 152;");
        if (c >= nb) return;
        if (STAG && c) __nanosleep(c * STAG);
        State st;
        st.mq = st.mkA = st.mkB = 0;
        st.qC[2] = c2[2]; st.qC[3] = c2[3];
        uint32_t pa[12], pb[16];
        pb[14] = cs[2]; pb[15] = cs[3];
#define metaAB pb[14]
#define metaC pb[15]
        const uint32_t one2 = cs[0], barid = cs[1], aAug = c2[0], oO = c2[1];
        const uint64_t dW = mkdesc(SB + SM_W, 128, 256);
        uint32_t bufo = SB + wg * 2 * BUF + BUF;
        int bstep = -BUF;
        uint32_t eN = SB + SM_E + c * ES, barN = SB + SM_BAR + c * 8;
        int left = (nb - c + NWG - 1) / NWG;
        uint8_t* gs = og + c * EB;
        float sa[24], sbb[28];
#define GO(i) *(uint32_t*)(gs + oO + (i) * 4)
#define QKA(SEL, Q, M) qk48<SEL>(sa, st.Q, dK, M)
#define QKB(SEL, Q, M) qk56<SEL>(sbb, st.Q, dK + 48, M)
#define PVA(N, O, D) pv<N, true>(O, pa, D); pv<N, false>(O, pa + 4, D + 16); pv<N, false>(O, pa + 8, D + 32)
#define PVB(N, O, D) pv<N, false>(O, pb, D + 48); pv<N, false>(O, pb + 4, D + 64); pv<N, false>(O, pb + 8, D + 80); pv<N, false>(O, pb + 12, D + 96)
#define EXPA() exp_block<0, 12>(sa, pa, one2, sh16); pin<12>(pa)
#define EXPB() exp_block<12, 14>(sbb, pb, one2, sh16); pin<14>(pb)
        {
            float d0[32], d1[32];
            PROF_MARK(2);
            pin<4>(a0); pin<4>(a1);
            WG_ARRIVE();
            proj64(d0, a0, dW);
            proj64(d1, a1, dW);
            WG_COMMIT();
            WG_WAIT(0);
            pin<32>(d0); pin<32>(d1);
            cvt_kv(st, d0, bufo - BUF + ad[2]);
            cvt_kv(st, d1, bufo - BUF + ad[3]);
            asm volatile("fence.proxy.async.shared::cta;" ::: "memory");
            cvt_qr0(st, d0 + 16, aAug);
            cvt_qr1(st, d1 + 16);
            asm volatile("bar.sync %0, 128;" ::"r"(barid) : "memory");
        }
        PROF_MARK(3);
#pragma unroll 1
        do {
            const uint32_t kLo = ((bufo + bstep) >> 4) + (COL >> 4 << 16);
            const uint32_t vLo = kLo + ((OFF_V >> 4) + ((8 - (COL >> 4)) << 16));
            const uint64_t dK = desc64(kLo, 8), dVA = desc64(vLo, 2 * COL >> 4), dV = desc64(vLo, COL >> 4);
            const uint64_t dVB = dV + (COL >> 4);
            float oA[8], oB[8], oC[12];
            WG_ARRIVE();
            QKA(0, qA, metaAB);
            WG_COMMIT();
            QKB(0, qA, metaAB);
            WG_COMMIT();
            WG_WAIT(1);
            pin<24>(sa);
            EXPA();
            WG_ARRIVE();
            QKA(1, qB, metaAB);
            PVA(16, oA, dVA);
            WG_COMMIT();
            WG_WAIT(1);
            pin<28>(sbb);
            EXPB();
            WG_ARRIVE();
            QKB(1, qB, metaAB);
            PVB(16, oA, dVA);
            WG_COMMIT();
            WG_WAIT(1);
            pin<24>(sa);
            EXPA();
            WG_ARRIVE();
            QKA(0, qC, metaC);
            PVA(16, oB, dVB);
            WG_COMMIT();
            WG_WAIT(1);
            pin<28>(sbb); pin<8>(oA);
            GO(0) = fin(oA[0], oA[1], oA[4], st.r[0]);
            GO(32) = fin(oA[2], oA[3], oA[6], st.r[1]);
            EXPB();
            WG_ARRIVE();
            QKB(0, qC, metaC);
            PVB(16, oB, dVB);
            WG_COMMIT();
            if (--left) { eN += NWG * ES; barN += NWG * 8; }
            mbar_wait(barN, 0);
            ldsm4(a0, eN + ad[0]);
            WG_WAIT(1);
            pin<24>(sa);
            EXPA();
            float d0[32], d1[32];
            WG_ARRIVE();
            proj64(d0, a0, dW);
            PVA(24, oC, dV);
            WG_COMMIT();
            WG_WAIT(1);
            pin<28>(sbb); pin<8>(oB);
            ldsm4(a1, eN + ad[1]);
            GO(4) = fin(oB[0], oB[1], oB[4], st.r[2]);
            GO(36) = fin(oB[2], oB[3], oB[6], st.r[3]);
            EXPB();
            WG_ARRIVE();
            proj64(d1, a1, dW);
            PVB(24, oC, dV);
            WG_COMMIT();
            WG_WAIT(1);
            pin<32>(d0);
            cvt_kv(st, d0, bufo + ad[2]);
            cvt_qr0(st, d0 + 16, aAug);
            WG_WAIT(0);
            pin<32>(d1); pin<12>(oC);
            cvt_kv(st, d1, bufo + ad[3]);
            asm volatile("fence.proxy.async.shared::cta;" ::: "memory");
            GO(64) = fin(oC[0], oC[1], oC[8], st.r[4]);
            GO(68) = fin(oC[6], oC[7], oC[10], st.r[5]);
            cvt_qr1(st, d1 + 16);
            asm volatile("bar.sync %0, 128;" ::"r"(barid) : "memory");
            gs += NWG * EB;
            bufo += bstep; bstep = -bstep;
        } while (left);
        PROF_MARK(30);
        const float x0 = __uint_as_float(st.mq << 16), x1 = __uint_as_float(st.mq & 0xFFFF0000u);
        const float y0 = __uint_as_float(st.mkA << 16), y1 = __uint_as_float(st.mkA & 0xFFFF0000u);
        const float y2 = __uint_as_float(st.mkB << 16), y3 = __uint_as_float(st.mkB & 0xFFFF0000u);
        float nq = TRK ? x0 + x1 : x0 * x0 + x1 * x1;
        float nk = TRK ? y0 + y1 : y0 * y0 + y1 * y1 + y2 * y2 + y3 * y3;
        nq += __shfl_xor_sync(0xffffffffu, nq, 1);
        nk += __shfl_xor_sync(0xffffffffu, nk, 2);
        nq += __shfl_xor_sync(0xffffffffu, nq, 2);
        if (wg_any(!(nq <= SLIMIT * QSCALE && nk <= SLIMIT / QSCALE), barid)) {
            const uint32_t uq = __reduce_max_sync(0xffffffffu, __float_as_uint(nq) & 0x7FFFFFFFu);
            const uint32_t uk = __reduce_max_sync(0xffffffffu, __float_as_uint(nk) & 0x7FFFFFFFu);
            if (lane == 0) { red[wid] = uq; red[16 + wid] = uk; }
            asm volatile("bar.sync %0, 128;" ::"r"(barid) : "memory");
            const float bq = __uint_as_float(__reduce_max_sync(0xffffffffu, red[wg * 4 + q]));
            const float bk = __uint_as_float(__reduce_max_sync(0xffffffffu, red[16 + wg * 4 + q]));
            if (!(bq * bk <= SLIMIT * SLIMIT)) {
#pragma unroll 1
                for (int lb = c; lb < nb; lb += NWG)
                    slow_path(e + (size_t)(b0 + lb) * (F * 16), wq, wk, wv, wr, out + (size_t)(b0 + lb) * (F * 16),
                              (float*)(smem + wg * 2 * BUF), tid & 127, barid, false);
            }
        }
        PROF_MARK(32); PROF_GT(1);
    }
}

}

extern "C" void kernel_launch(void* const* d_in, const int* in_sizes, int n_in, void* d_out, int out_size) {
    static int sms = 0;
    if (!sms) {
        cudaDeviceGetAttribute(&sms, cudaDevAttrMultiProcessorCount, 0);
        cudaFuncSetAttribute(autoint_kernel, cudaFuncAttributeMaxDynamicSharedMemorySize, SM_TOTAL);
    }
    const int B = in_sizes[0] / (F * 16);
    int grid = sms < B ? sms : B;
    if (grid * MAXB < B) grid = (B + MAXB - 1) / MAXB;
    const int base = B / grid, rem = B % grid;
    const int moved = (base & 1) && rem * (base + 1) <= grid - rem ? rem * (base + 1) : 0;
    autoint_kernel<<<grid, 512, SM_TOTAL>>>(
        (const __nv_bfloat16*)d_in[0], (const __nv_bfloat16*)d_in[1], (const __nv_bfloat16*)d_in[2],
        (const __nv_bfloat16*)d_in[3], (const __nv_bfloat16*)d_in[4], (__nv_bfloat16*)d_out, base, rem, moved, 65536u);
}
```
